```python
import torch

def _softmax(x, axis=-1):
    return torch.softmax(x, dim=axis)
def _gelu(x):
    return torch.nn.functional.gelu(x, approximate="tanh")
def _silu(x):
    return torch.nn.functional.silu(x)
def _sigmoid(x):
    return torch.sigmoid(x)
def _layernorm(x, axis=-1, eps=1e-5):
    m = x.mean(dim=axis, keepdim=True)
    v = x.var(dim=axis, keepdim=True, unbiased=False)
    return (x - m) / torch.sqrt(v + eps)
def _scatter_add(tgt, idx, src, axis=0):
    return tgt.clone().index_add_(axis, idx, src)
def _segment_sum(src, seg, n):
    out = torch.zeros((n,) + src.shape[1:], dtype=src.dtype)
    return out.index_add_(0, seg, src)
def _pad(x, pw):
    flat = tuple(v for pair in reversed(pw) for v in pair)
    return torch.nn.functional.pad(x, flat)

kernel_name = 'standalone__implicit_deq__vision'

def setup_inputs():

    _w = (lambda a: (lambda t: t.to(torch.bfloat16) if t.is_floating_point() else t)(torch.as_tensor(a)))
    H = W = 224
    C = 96
    Wz = (lambda *s: torch.randn(*s, dtype=torch.bfloat16) * 0.4)(C, C) * (0.3 / C ** 0.5)
    Wx = (lambda *s: torch.randn(*s, dtype=torch.bfloat16) * 0.4)(C, C) * (1.0 / C ** 0.5)
    bb = (lambda *s: torch.randn(*s, dtype=torch.bfloat16) * 0.4)(C) * 0.1
    return {
        "x": _w((lambda *s: torch.randn(*s, dtype=torch.bfloat16) * 0.4)(1, H, W, C)),
        "w_z": _w(Wz),
        "w_x": _w(Wx),
        "b": _w(bb),
    }

def reference(x, w_z, w_x, b):
    B, H, W, C = x.shape
    inj = torch.einsum("bhwc,cd->bhwd", x, w_x) + b
    z = torch.zeros_like(x)
    for _ in range(25):
        z = torch.tanh(torch.einsum("bhwc,cd->bhwd", z, w_z) + inj)
    return z
```

```cpp
#include <cuda_runtime.h>
#include <cuda_bf16.h>
#include <stdint.h>

#define LUTMASK 0x111111u
#define NWG 3

namespace {

constexpr int C = 96;
constexpr int NITER = 25;
constexpr int NTHREADS = NWG * 128;

constexpr uint32_t LUT_LO = 0x3DB8u;
constexpr uint32_t LUT_HI = 0x405Eu;
constexpr int LUT_N = LUT_HI - LUT_LO + 1;

constexpr int SM_WX = 0;
constexpr int SM_WZ = 18432;
constexpr int SM_LUT = 36864;
constexpr int SM_TOTAL = SM_LUT + (LUTMASK ? LUT_N * 128 : 0);

#define WG_FENCE() asm volatile("wgmma.fence.sync.aligned;" ::: "memory")
#define WG_COMMIT() asm volatile("wgmma.commit_group.sync.aligned;" ::: "memory")
#define WG_WAIT0() asm volatile("wgmma.wait_group.sync.aligned 0;" ::: "memory")

template <int SCALE_D>
__device__ __forceinline__ void wgmma96(float (&d)[48], uint32_t a0, uint32_t a1, uint32_t a2, uint32_t a3,
                                        uint64_t desc) {
    asm volatile(
        "{\n.reg .pred p;\nsetp.ne.b32 p, %53, 0;\n"
        "wgmma.mma_async.sync.aligned.m64n96k16.f32.bf16.bf16 "
        "{%0,%1,%2,%3,%4,%5,%6,%7,%8,%9,%10,%11,%12,%13,%14,%15,%16,%17,%18,%19,%20,%21,%22,%23,"
        "%24,%25,%26,%27,%28,%29,%30,%31,%32,%33,%34,%35,%36,%37,%38,%39,%40,%41,%42,%43,%44,%45,%46,%47},"
        "{%48,%49,%50,%51}, %52, p, 1, 1, 1;\n}\n"
        : "+f"(d[0]), "+f"(d[1]), "+f"(d[2]), "+f"(d[3]), "+f"(d[4]), "+f"(d[5]), "+f"(d[6]), "+f"(d[7]),
          "+f"(d[8]), "+f"(d[9]), "+f"(d[10]), "+f"(d[11]), "+f"(d[12]), "+f"(d[13]), "+f"(d[14]), "+f"(d[15]),
          "+f"(d[16]), "+f"(d[17]), "+f"(d[18]), "+f"(d[19]), "+f"(d[20]), "+f"(d[21]), "+f"(d[22]), "+f"(d[23]),
          "+f"(d[24]), "+f"(d[25]), "+f"(d[26]), "+f"(d[27]), "+f"(d[28]), "+f"(d[29]), "+f"(d[30]), "+f"(d[31]),
          "+f"(d[32]), "+f"(d[33]), "+f"(d[34]), "+f"(d[35]), "+f"(d[36]), "+f"(d[37]), "+f"(d[38]), "+f"(d[39]),
          "+f"(d[40]), "+f"(d[41]), "+f"(d[42]), "+f"(d[43]), "+f"(d[44]), "+f"(d[45]), "+f"(d[46]), "+f"(d[47])
        : "r"(a0), "r"(a1), "r"(a2), "r"(a3), "l"(desc), "n"(SCALE_D));
}

__device__ __forceinline__ void fence_acc(float (&d)[48]) {
#pragma unroll
    for (int i = 0; i < 48; i++) asm volatile("" : "+f"(d[i])::"memory");
}

__device__ __forceinline__ uint64_t make_desc(uint32_t addr) {
    return (uint64_t)((addr & 0x3FFFF) >> 4) | ((uint64_t)(1536 >> 4) << 16) | ((uint64_t)(128 >> 4) << 32);
}

__device__ __forceinline__ uint32_t pack_bf16(float lo, float hi) {
    uint32_t r;
    asm("cvt.rn.bf16x2.f32 %0, %1, %2;" : "=r"(r) : "f"(hi), "f"(lo));
    return r;
}
__device__ __forceinline__ uint32_t add_bf16x2(uint32_t a, uint32_t b) {
    uint32_t r;
    asm("add.rn.bf16x2 %0, %1, %2;" : "=r"(r) : "r"(a), "r"(b));
    return r;
}
__device__ __forceinline__ float tanh_mufu(float x) {
    float r;
    asm("tanh.approx.f32 %0, %1;" : "=f"(r) : "f"(x));
    return r;
}
__device__ __forceinline__ float addw_hi(uint32_t pk, uint32_t inj) {
    uint32_t r;
    asm("fma.rn.bf16x2 %0, %1, %2, %3;" : "=r"(r) : "r"(pk), "r"(0x3F800000u), "r"(inj));
    return __uint_as_float(r);
}
__device__ __forceinline__ float addw_lo(uint32_t pk, uint32_t inj) {
    uint32_t r;
    asm("{\n.reg .b16 l, h;\n.reg .b32 t;\nmov.b32 {l, h}, %1;\nmov.b32 t, {l, l};\n"
        "fma.rn.bf16x2 %0, t, %2, %3;\n}\n"
        : "=r"(r)
        : "r"(pk), "r"(0x3F800000u), "r"(inj));
    return __uint_as_float(r);
}
__device__ __forceinline__ uint32_t tanh_lut(uint32_t p, uint32_t lutbase) {
    uint32_t c, a0, a1, t0, t1, t, r;
    asm("{\n.reg .b32 u;\nabs.bf16x2 u, %1;\nmin.bf16x2 u, u, %2;\nmax.bf16x2 %0, u, %3;\n}\n"
        : "=r"(c)
        : "r"(p), "r"(LUT_HI * 0x10001u), "r"(LUT_LO * 0x10001u));
    asm("dp2a.lo.u32.u32 %0, %1, %2, %3;" : "=r"(a0) : "r"(c), "r"(0x80000080u), "r"(lutbase));
    asm("dp2a.hi.u32.u32 %0, %1, %2, %3;" : "=r"(a1) : "r"(c), "r"(0x80000080u), "r"(lutbase));
    asm("ld.shared.b32 %0, [%1];" : "=r"(t0) : "r"(a0));
    asm("ld.shared.b32 %0, [%1];" : "=r"(t1) : "r"(a1));
    asm("prmt.b32 %0, %1, %2, 0x5410;" : "=r"(t) : "r"(t0), "r"(t1));
    asm("min.NaN.xorsign.abs.bf16x2 %0, %1, %2;" : "=r"(r) : "r"(p), "r"(t));
    return r;
}

template <int I>
__device__ __forceinline__ uint32_t act(uint32_t pk, uint32_t injA, uint32_t injB, uint32_t lutbase) {
    if ((LUTMASK >> I) & 1) {
        return tanh_lut(add_bf16x2(pk, injA), lutbase);
    } else {
        return pack_bf16(tanh_mufu(addw_lo(pk, injA)), tanh_mufu(addw_hi(pk, injB)));
    }
}

template <int KK>
__device__ __forceinline__ void act_chunk(uint32_t (&a)[24], const uint32_t (&injA)[24], const uint32_t (&injB)[24],
                                          uint32_t lutbase) {
    a[4 * KK + 0] = act<4 * KK + 0>(a[4 * KK + 0], injA[4 * KK + 0], injB[4 * KK + 0], lutbase);
    a[4 * KK + 1] = act<4 * KK + 1>(a[4 * KK + 1], injA[4 * KK + 1], injB[4 * KK + 1], lutbase);
    a[4 * KK + 2] = act<4 * KK + 2>(a[4 * KK + 2], injA[4 * KK + 2], injB[4 * KK + 2], lutbase);
    a[4 * KK + 3] = act<4 * KK + 3>(a[4 * KK + 3], injA[4 * KK + 3], injB[4 * KK + 3], lutbase);
}

template <int KK>
__device__ __forceinline__ void step_chunk(float (&acc)[48], uint32_t (&a)[24], const uint32_t (&injA)[24],
                                           const uint32_t (&injB)[24], uint32_t lutbase, uint64_t dz) {
    act_chunk<KK>(a, injA, injB, lutbase);
    WG_FENCE();
    wgmma96<(KK > 0)>(acc, a[4 * KK], a[4 * KK + 1], a[4 * KK + 2], a[4 * KK + 3], dz + KK * (3072 >> 4));
}

__device__ __forceinline__ uint4 ldg_nc(const void* p) {
    uint4 v;
    asm volatile("ld.global.nc.L1::no_allocate.v4.u32 {%0,%1,%2,%3}, [%4];"
                 : "=r"(v.x), "=r"(v.y), "=r"(v.z), "=r"(v.w)
                 : "l"(p));
    return v;
}

__device__ __forceinline__ int phys_ch(int l) {
    int j = l >> 3, t = (l & 7) >> 1, e = l & 1;
    return 32 * (j >> 2) + 8 * t + 2 * (j & 3) + e;
}

__device__ __forceinline__ void load_x(uint32_t (&a)[24], const __nv_bfloat16* x, int tile, int rowoff) {
    const __nv_bfloat16* p = x + (size_t)tile * (64 * C) + rowoff;
#pragma unroll
    for (int h = 0; h < 2; h++)
#pragma unroll
        for (int q = 0; q < 3; q++) {
            uint4 v = ldg_nc(p + h * 8 * C + q * 32);
            a[8 * q + 0 + h] = v.x;
            a[8 * q + 2 + h] = v.y;
            a[8 * q + 4 + h] = v.z;
            a[8 * q + 6 + h] = v.w;
        }
}

__global__ void __launch_bounds__(NTHREADS, 1)
deq_kernel(const __nv_bfloat16* __restrict__ x, const __nv_bfloat16* __restrict__ wz,
           const __nv_bfloat16* __restrict__ wx, const __nv_bfloat16* __restrict__ bias,
           __nv_bfloat16* __restrict__ out, int ntiles) {
    extern __shared__ __align__(1024) uint8_t smem[];
    const int tid = threadIdx.x;
    const int wg = tid >> 7;
    const int lane = tid & 31;
    const int wrow = ((tid >> 5) & 3) * 16 + (lane >> 2);
    const int rowoff = wrow * C + (lane & 3) * 8;
    const uint32_t sbase = (uint32_t)__cvta_generic_to_shared(smem);

    int tile = wg * gridDim.x + blockIdx.x;
    const int tstride = NWG * gridDim.x;

    uint32_t a[24];
    if (tile < ntiles) load_x(a, x, tile, rowoff);

    for (int task = tid; task < 576; task += NTHREADS) {
        const int m = task >= 288;
        const int r = task - m * 288;
        const int q = r / 96, k = r - q * 96;
        const __nv_bfloat16* src = (m ? wz : wx) + phys_ch(k) * C + q * 32;
        uint4 v0 = ldg_nc(src), v1 = ldg_nc(src + 8), v2 = ldg_nc(src + 16), v3 = ldg_nc(src + 24);
        uint8_t* dst = smem + (m ? SM_WZ : SM_WX) + (k >> 3) * 1536 + q * 512 + (k & 7) * 16;
        *(uint4*)(dst + 0) = make_uint4(v0.x, v1.x, v2.x, v3.x);
        *(uint4*)(dst + 128) = make_uint4(v0.y, v1.y, v2.y, v3.y);
        *(uint4*)(dst + 256) = make_uint4(v0.z, v1.z, v2.z, v3.z);
        *(uint4*)(dst + 384) = make_uint4(v0.w, v1.w, v2.w, v3.w);
    }
    if (LUTMASK) {
        for (int e = tid >> 3; e < LUT_N; e += NTHREADS / 8) {
            float t = tanh_mufu(__uint_as_float((LUT_LO + e) << 16));
            uint32_t v = pack_bf16(t, 0.f);
            *(uint4*)(smem + SM_LUT + e * 128 + (tid & 7) * 16) = make_uint4(v, v, v, v);
        }
    }
    asm volatile("fence.proxy.async.shared::cta;" ::: "memory");
    __syncthreads();

    const uint32_t lutbase = sbase + SM_LUT + lane * 4 - LUT_LO * 128;
    const uint64_t dx = make_desc(sbase + SM_WX);
    const uint64_t dz = make_desc(sbase + SM_WZ);

    float acc[48];
#pragma unroll
    for (int i = 0; i < 48; i++) acc[i] = 0.f;

    bool first = true;
#pragma unroll 1
    for (; tile < ntiles; tile += tstride) {
        if (!first) load_x(a, x, tile, rowoff);
        first = false;
        uint32_t bb[12];
#pragma unroll
        for (int q = 0; q < 3; q++) {
            uint4 v = ldg_nc(bias + q * 32 + (lane & 3) * 8);
            bb[4 * q] = v.x; bb[4 * q + 1] = v.y; bb[4 * q + 2] = v.z; bb[4 * q + 3] = v.w;
        }
        WG_FENCE();
        wgmma96<0>(acc, a[0], a[1], a[2], a[3], dx);
#pragma unroll
        for (int kk = 1; kk < 6; kk++)
            wgmma96<1>(acc, a[4 * kk], a[4 * kk + 1], a[4 * kk + 2], a[4 * kk + 3], dx + kk * (3072 >> 4));
        WG_COMMIT();
        WG_WAIT0();
        fence_acc(acc);

        uint32_t injA[24], injB[24];
#pragma unroll
        for (int i = 0; i < 24; i++) {
            uint32_t inj = add_bf16x2(pack_bf16(acc[2 * i], acc[2 * i + 1]), bb[i >> 1]);
            if ((LUTMASK >> i) & 1) {
                injA[i] = inj;
                injB[i] = 0;
            } else {
                injA[i] = inj << 16;
                injB[i] = inj & 0xFFFF0000u;
            }
            a[i] = 0;
        }

#pragma unroll 1
        for (int it = 1; it < NITER; it++) {
            step_chunk<0>(acc, a, injA, injB, lutbase, dz);
            step_chunk<1>(acc, a, injA, injB, lutbase, dz);
            step_chunk<2>(acc, a, injA, injB, lutbase, dz);
            step_chunk<3>(acc, a, injA, injB, lutbase, dz);
            step_chunk<4>(acc, a, injA, injB, lutbase, dz);
            step_chunk<5>(acc, a, injA, injB, lutbase, dz);
            WG_COMMIT();
            WG_WAIT0();
            fence_acc(acc);
#pragma unroll
            for (int i = 0; i < 24; i++) a[i] = pack_bf16(acc[2 * i], acc[2 * i + 1]);
        }
        act_chunk<0>(a, injA, injB, lutbase);
        act_chunk<1>(a, injA, injB, lutbase);
        act_chunk<2>(a, injA, injB, lutbase);
        act_chunk<3>(a, injA, injB, lutbase);
        act_chunk<4>(a, injA, injB, lutbase);
        act_chunk<5>(a, injA, injB, lutbase);

        __nv_bfloat16* o = out + (size_t)tile * (64 * C) + rowoff;
#pragma unroll
        for (int h = 0; h < 2; h++)
#pragma unroll
            for (int q = 0; q < 3; q++)
                *(uint4*)(o + h * 8 * C + q * 32) =
                    make_uint4(a[8 * q + h], a[8 * q + 2 + h], a[8 * q + 4 + h], a[8 * q + 6 + h]);
    }
}

}

extern "C" void kernel_launch(void* const* d_in, const int* in_sizes, int n_in, void* d_out, int out_size) {
    const __nv_bfloat16* x = (const __nv_bfloat16*)d_in[0];
    const __nv_bfloat16* wz = (const __nv_bfloat16*)d_in[1];
    const __nv_bfloat16* wx = (const __nv_bfloat16*)d_in[2];
    const __nv_bfloat16* b = (const __nv_bfloat16*)d_in[3];
    __nv_bfloat16* out = (__nv_bfloat16*)d_out;
    static int nsm = 0;
    if (!nsm) {
        int dev = 0;
        cudaGetDevice(&dev);
        cudaDeviceGetAttribute(&nsm, cudaDevAttrMultiProcessorCount, dev);
        cudaFuncSetAttribute(deq_kernel, cudaFuncAttributeMaxDynamicSharedMemorySize, SM_TOTAL);
    }
    const int ntiles = in_sizes[0] / (64 * C);
    deq_kernel<<<nsm, NTHREADS, SM_TOTAL>>>(x, wz, wx, b, out, ntiles);
}
```

```cpp
#include <cuda_runtime.h>
#include <cuda_bf16.h>
#include <stdint.h>

#define LUTMASK 0xC3CC00u
#define SEQ0   \
    5, 0, 1, 3, 4, 7, 6, 2, 10, 14, 11, 8, 43, 42, 13, 234, 15, 74, 22, 19, 12, 235, 75, 16, 9, 20, 23, 17, 96, \
    21, 46, 97, 47, 78, 238, 18, 79, 99, 239, 98, 160, 55, 200, 48, 80, 240, 100, 49, 54, 102, 81, 104, 101, \
    103, 86, 105, 87, 247, 241, 246, 138, 139, 160, 193, 194, 143, 109, 108, 142, 115, 114, 144, 145, 160, 195, \
    196, 151, 116, 117, 150, 160, 197
#define SEQ1   \
    0, 2, 3, 1, 10, 4, 5, 7, 8, 6, 9, 15, 19, 11, 13, 16, 14, 12, 17, 18, 42, 23, 22, 21, 20, 43, 75, 235, 46, \
    98, 96, 97, 234, 99, 47, 160, 74, 200, 100, 238, 78, 79, 101, 239, 48, 103, 102, 49, 81, 240, 80, 138, 241, \
    104, 54, 105, 139, 55, 160, 193, 194, 246, 87, 142, 108, 247, 143, 109, 86, 144, 145, 115, 114, 160, 150, \
    195, 196, 116, 151, 117, 160, 197
#define SEQK   \
    1, 2, 3, 5, 11, 6, 4, 0, 7, 8, 96, 14, 17, 16, 15, 9, 12, 10, 22, 18, 21, 19, 13, 43, 20, 75, 23, 42, 97, \
    47, 234, 99, 74, 98, 46, 235, 160, 78, 101, 49, 100, 79, 48, 105, 103, 139, 102, 238, 80, 241, 239, 200, \
    240, 81, 104, 138, 54, 86, 160, 193, 194, 246, 55, 247, 108, 143, 109, 145, 87, 142, 115, 114, 144, 160, \
    195, 196, 116, 150, 151, 117, 160, 197
#define SEQG   \
    5, 4, 0, 6, 3, 1, 7, 10, 2, 14, 11, 8, 42, 13, 74, 15, 9, 234, 43, 75, 22, 19, 16, 23, 235, 12, 20, 96, 17, \
    18, 21, 46, 238, 97, 47, 78, 239, 99, 79, 98, 160, 55, 48, 101, 80, 200, 240, 102, 49, 100, 54, 81, 241, 87, \
    86, 246, 104, 103, 247, 105, 138, 139, 160, 193, 194, 108, 143, 109, 114, 144, 142, 115, 145, 160, 151, 195, \
    196, 116, 117, 150, 160, 197
#define SEQ2   \
    0, 2, 3, 1, 4, 10, 7, 11, 6, 5, 8, 9, 15, 22, 13, 23, 14, 16, 19, 12, 18, 20, 17, 21, 42, 74, 234, 96, 43, \
    235, 75, 46, 98, 99, 78, 238, 47, 97, 100, 101, 160, 239, 200, 79, 103, 48, 240, 80, 138, 49, 81, 104, 54, \
    241, 105, 102, 139, 246, 86, 160, 193, 194, 55, 247, 87, 114, 108, 109, 142, 145, 144, 116, 115, 151, 143, \
    160, 117, 195, 196, 150, 160, 197
#define SEQL   \
    4, 0, 2, 3, 1, 5, 7, 10, 8, 6, 9, 15, 14, 11, 13, 19, 17, 18, 16, 42, 98, 23, 22, 21, 12, 20, 43, 96, 75, \
    235, 46, 97, 234, 99, 160, 74, 200, 238, 47, 48, 100, 78, 239, 79, 103, 102, 80, 101, 240, 49, 241, 104, 54, \
    81, 105, 139, 55, 138, 160, 193, 194, 87, 246, 109, 142, 108, 247, 143, 86, 114, 144, 115, 145, 150, 160, \
    195, 117, 196, 116, 151, 160, 197
#define KCHK 10

namespace {

constexpr int C = 96;
constexpr int NITER = 25;
constexpr int NTHREADS = 512;
constexpr int ROW_B = C * 2;
constexpr int TILE_B = 64 * ROW_B;
constexpr int W_B = C * ROW_B;
constexpr unsigned FULL = 0xFFFFFFFFu;

constexpr uint32_t LUT_LO = 0x2C00u;
constexpr uint32_t LUT_HI = 0x4400u;
constexpr int LUT_N = (LUT_HI - LUT_LO) / 8 + 1;

constexpr int SM_WX = 0;
constexpr int SM_WZ = W_B;
constexpr int SM_PA = 2 * W_B;
constexpr int SM_PB = SM_PA + 3 * TILE_B;
constexpr int SM_LUT = SM_PB + 3 * TILE_B;
constexpr int SM_BIAS = SM_LUT + LUT_N * 128;
constexpr int SM_LIST = SM_BIAS + ROW_B;
constexpr int SM_BAR = SM_LIST + 192;
constexpr int SM_CNT = SM_BAR + 96;
constexpr int SM_TOTAL = SM_CNT + 16;

#define WG_FENCE() asm volatile("wgmma.fence.sync.aligned;" ::: "memory")
#define WG_COMMIT() asm volatile("wgmma.commit_group.sync.aligned;" ::: "memory")
#define WG_WAIT0() asm volatile("wgmma.wait_group.sync.aligned 0;" ::: "memory")

#define OPS8(c, d, i) c(d[i]), c(d[i + 1]), c(d[i + 2]), c(d[i + 3]), c(d[i + 4]), c(d[i + 5]), c(d[i + 6]), c(d[i + 7])
#define OPS24(c, d, i) OPS8(c, d, i), OPS8(c, d, i + 8), OPS8(c, d, i + 16)
#define REGS24 "%0,%1,%2,%3,%4,%5,%6,%7,%8,%9,%10,%11,%12,%13,%14,%15,%16,%17,%18,%19,%20,%21,%22,%23"
#define REGS48 REGS24 ",%24,%25,%26,%27,%28,%29,%30,%31,%32,%33,%34,%35,%36,%37,%38,%39,%40,%41,%42,%43,%44,%45,%46,%47"

template <bool ACC>
__device__ __forceinline__ void mma_bf16(float (&d)[48], const uint32_t* a, uint64_t desc) {
    if (ACC)
        asm volatile("wgmma.mma_async.sync.aligned.m64n96k16.f32.bf16.bf16 {" REGS48 "}, {%48,%49,%50,%51}, %52, 1, 1, 1, 1;"
                     : OPS24("+f", d, 0), OPS24("+f", d, 24)
                     : "r"(a[0]), "r"(a[1]), "r"(a[2]), "r"(a[3]), "l"(desc));
    else
        asm volatile("wgmma.mma_async.sync.aligned.m64n96k16.f32.bf16.bf16 {" REGS48 "}, {%48,%49,%50,%51}, %52, 0, 1, 1, 1;"
                     : OPS24("=f", d, 0), OPS24("=f", d, 24)
                     : "r"(a[0]), "r"(a[1]), "r"(a[2]), "r"(a[3]), "l"(desc));
}
template <bool ACC>
__device__ __forceinline__ void mma_f16(uint32_t (&d)[24], const uint32_t* a, uint64_t desc) {
    if (ACC)
        asm volatile("wgmma.mma_async.sync.aligned.m64n96k16.f16.f16.f16 {" REGS24 "}, {%24,%25,%26,%27}, %28, 1, 1, 1, 1;"
                     : OPS24("+r", d, 0)
                     : "r"(a[0]), "r"(a[1]), "r"(a[2]), "r"(a[3]), "l"(desc));
    else
        asm volatile("wgmma.mma_async.sync.aligned.m64n96k16.f16.f16.f16 {" REGS24 "}, {%24,%25,%26,%27}, %28, 0, 1, 1, 1;"
                     : OPS24("=r", d, 0)
                     : "r"(a[0]), "r"(a[1]), "r"(a[2]), "r"(a[3]), "l"(desc));
}
template <int N>
__device__ __forceinline__ void fence_regs(float (&d)[N]) {
#pragma unroll
    for (int i = 0; i < N; i++) asm volatile("" : "+f"(d[i])::"memory");
}
template <int N>
__device__ __forceinline__ void fence_regs(uint32_t (&d)[N]) {
#pragma unroll
    for (int i = 0; i < N; i++) asm volatile("" : "+r"(d[i])::"memory");
}
__device__ __forceinline__ uint64_t make_desc(uint32_t addr) {
    return (uint64_t)((addr & 0x3FFFF) >> 4) | ((uint64_t)(1536 >> 4) << 16) | ((uint64_t)(128 >> 4) << 32);
}

__device__ __forceinline__ uint32_t pack_bf16(float lo, float hi) {
    uint32_t r;
    asm("cvt.rn.bf16x2.f32 %0, %1, %2;" : "=r"(r) : "f"(hi), "f"(lo));
    return r;
}
__device__ __forceinline__ uint32_t pack_f16(float lo, float hi) {
    uint32_t r;
    asm("cvt.rn.satfinite.f16x2.f32 %0, %1, %2;" : "=r"(r) : "f"(hi), "f"(lo));
    return r;
}
__device__ __forceinline__ void unpack_f16(uint32_t v, float& lo, float& hi) {
    asm("{\n.reg .b16 l, h;\nmov.b32 {l, h}, %2;\ncvt.f32.f16 %0, l;\ncvt.f32.f16 %1, h;\n}\n" : "=f"(lo), "=f"(hi) : "r"(v));
}
__device__ __forceinline__ uint32_t bf2_to_h2(uint32_t v) {
    return pack_f16(__uint_as_float(v << 16), __uint_as_float(v & 0xFFFF0000u));
}
__device__ __forceinline__ uint32_t h2_to_bf2(uint32_t v) {
    float lo, hi;
    unpack_f16(v, lo, hi);
    return pack_bf16(lo, hi);
}
__device__ __forceinline__ uint32_t add_bf16x2(uint32_t a, uint32_t b) {
    uint32_t r;
    asm("add.rn.bf16x2 %0, %1, %2;" : "=r"(r) : "r"(a), "r"(b));
    return r;
}
__device__ __forceinline__ uint32_t add_f16x2(uint32_t a, uint32_t b) {
    uint32_t r;
    asm("add.rn.f16x2 %0, %1, %2;" : "=r"(r) : "r"(a), "r"(b));
    return r;
}
__device__ __forceinline__ float tanh_f32(float x) {
    float r;
    asm("tanh.approx.f32 %0, %1;" : "=f"(r) : "f"(x));
    return r;
}

struct Inv {
    uint64_t dz[6];
    uint32_t lut;
    uint32_t neglo;
    uint32_t mul;
    uint32_t zero;
};

enum { P_SUM, P_INJ  , P_GIVEN, P_LAST   };
enum { OP_ADD, OP_IDX, OP_LD0, OP_TANH, OP_FIN, OP_FENCE, OP_MMA, OP_LD1 };
template <int... S> struct Seq {
    static constexpr bool valid() {
        const int s[] = {S...};
        unsigned done[8] = {0, 0, 0, 0, 0, 0, 0, 0}, fenced = 0, added = 0;
        int chunk = 0;
        for (int v : s) {
            const int op = v >> 5, i = v & 31;
            if (op == OP_FENCE) { fenced = done[OP_TANH] | done[OP_FIN]; added = done[OP_ADD]; continue; }
            if (op == OP_MMA) {
                if (i != (chunk ? chunk : 8) || added != 0xFFFFFFu || ((fenced >> (4 * chunk)) & 15) != 15) return false;
                chunk++;
                continue;
            }
            const unsigned need = op == OP_ADD ? ~0u : op == OP_FIN ? done[OP_LD0] & done[OP_LD1]
                                  : done[op == OP_LD0 || op == OP_LD1 ? OP_IDX : OP_ADD];
            if (((done[op] >> i) & 1) || !((need >> i) & 1)) return false;
            done[op] |= 1u << i;
        }
        return chunk == 6 && done[OP_FIN] == LUTMASK && done[OP_TANH] == (0xFFFFFFu & ~LUTMASK);
    }
};
static_assert(Seq<SEQ0>::valid() && Seq<SEQ1>::valid() && Seq<SEQK>::valid(), "bad sequence");
static_assert(Seq<SEQG>::valid() && Seq<SEQ2>::valid() && Seq<SEQL>::valid(), "bad sequence");
static_assert(((LUTMASK ^ (LUTMASK >> 1)) & 0x555555u) == 0, "both rows of a thread must use the same tanh per column");
struct Tmp { uint32_t u[24], t0[24], t1[24]; };
template <int MODE, int S>
__device__ __forceinline__ void step_op(uint32_t (&h)[24], uint32_t (&a)[24], uint32_t (&p)[24], const uint32_t (&inj)[24],
                                        Tmp& t, const Inv& c) {
    constexpr int op = S >> 5, i = S & 31;
    if (op == OP_ADD) {
        if (MODE == P_INJ) p[i] = inj[i];
        if (MODE == P_SUM || MODE == P_LAST) asm volatile("add.rn.f16x2 %0, %1, %2;" : "=r"(p[i]) : "r"(h[i]), "r"(inj[i]));
    }
    if (op == OP_IDX)
        asm volatile("{\n.reg .b32 u;\nand.b32 u, %1, 0x7FF87FF8;\nadd.s16x2 u, u, %2;\nmin.s16x2.relu %0, u, %3;\n}\n"
                     : "=r"(t.u[i]) : "r"(p[i]), "r"(c.neglo), "r"((LUT_HI - LUT_LO) * 0x10001u));
    if (op == OP_LD0)
        asm volatile("{\n.reg .b32 a;\ndp2a.lo.u32.u32 a, %1, %2, %3;\nld.shared.b32 %0, [a];\n}\n"
                     : "=r"(t.t0[i]) : "r"(t.u[i]), "r"(c.mul), "r"(c.lut));
    if (op == OP_LD1)
        asm volatile("{\n.reg .b32 a;\ndp2a.hi.u32.u32 a, %1, %2, %3;\nld.shared.b32 %0, [a];\n}\n"
                     : "=r"(t.t1[i]) : "r"(t.u[i]), "r"(c.mul), "r"(c.lut));
    if (op == OP_TANH) asm volatile("tanh.approx.f16x2 %0, %1;" : "=r"(a[i]) : "r"(p[i]));
    if (op == OP_FIN)
        asm volatile("{\n.reg .b32 t;\nprmt.b32 t, %2, %3, 0x5410;\nmin.NaN.xorsign.abs.f16x2 %0, %1, t;\n}\n"
                     : "=r"(a[i]) : "r"(p[i]), "r"(t.t0[i]), "r"(t.t1[i]));
    if (op == OP_FENCE && MODE != P_LAST) WG_FENCE();
    if (op == OP_MMA && MODE != P_LAST) {
        if (i & 8) mma_f16<false>(h, &a[4 * (i & 7)], c.dz[i & 7]);
        else mma_f16<true>(h, &a[4 * (i & 7)], c.dz[i & 7]);
    }
}
template <int MODE, int... S>
__device__ __forceinline__ void step(Seq<S...>, uint32_t (&h)[24], uint32_t (&a)[24], uint32_t (&p)[24],
                                     const uint32_t (&inj)[24], const Inv& c) {
    Tmp t;
    (step_op<MODE, S>(h, a, p, inj, t, c), ...);
    if (MODE == P_LAST) return;
    WG_COMMIT();
    WG_WAIT0();
    fence_regs(h);
}

__device__ __forceinline__ uint4 lds128(uint32_t addr) {
    uint4 v;
    asm volatile("ld.shared.v4.u32 {%0,%1,%2,%3}, [%4];" : "=r"(v.x), "=r"(v.y), "=r"(v.z), "=r"(v.w) : "r"(addr) : "memory");
    return v;
}
__device__ __forceinline__ int lds32(uint32_t addr) {
    int v;
    asm volatile("ld.shared.u32 %0, [%1];" : "=r"(v) : "r"(addr) : "memory");
    return v;
}
__device__ __forceinline__ int lds8(uint32_t addr) {
    int v;
    asm volatile("ld.shared.u8 %0, [%1];" : "=r"(v) : "r"(addr) : "memory");
    return v;
}
__device__ __forceinline__ void sts32(uint32_t addr, uint32_t v) {
    asm volatile("st.shared.u32 [%0], %1;" ::"r"(addr), "r"(v) : "memory");
}
__device__ __forceinline__ void sts8_if(uint32_t addr, int v, bool pred) {
    asm volatile("{\n.reg .pred p;\nsetp.ne.s32 p, %2, 0;\n@p st.shared.u8 [%0], %1;\n}\n" ::"r"(addr), "r"(v), "r"((int)pred) : "memory");
}
__device__ __forceinline__ int atoms_add_lane0(uint32_t addr, int v, int lane) {
    int r = 0;
    asm volatile("{\n.reg .pred p;\nsetp.eq.s32 p, %3, 0;\n@p atom.shared.add.u32 %0, [%1], %2;\n}\n"
                 : "+r"(r) : "r"(addr + lane * 4), "r"(v), "r"(lane) : "memory");
    return r;
}
__device__ __forceinline__ void mbar_init(uint32_t bar, uint32_t count) {
    asm volatile("mbarrier.init.shared::cta.b64 [%0], %1;" ::"r"(bar), "r"(count) : "memory");
}
__device__ __forceinline__ void mbar_arrive_warp(uint32_t bar, int lane) {
    __syncwarp();
    asm volatile("{\n.reg .pred p;\nsetp.eq.s32 p, %1, 0;\n@p mbarrier.arrive.shared::cta.b64 _, [%0];\n}\n" ::"r"(bar), "r"(lane) : "memory");
}
__device__ __forceinline__ void mbar_wait(uint32_t bar) {
    asm volatile(
        "{\n.reg .pred p;\n.reg .u32 n;\nmov.u32 n, 0;\n"
        "LAB_WAIT:\n"
        "mbarrier.try_wait.parity.shared::cta.b64 p, [%0], 0, 20000;\n"
        "@p bra LAB_DONE;\n"
        "add.u32 n, n, 1;\nsetp.lt.u32 p, n, 0x400000;\n@p bra LAB_WAIT;\ntrap;\n"
        "LAB_DONE:\n}\n" ::"r"(bar)
        : "memory");
}
__device__ __forceinline__ void mbar_expect(uint32_t bar, uint32_t bytes) {
    asm volatile("mbarrier.arrive.expect_tx.shared::cta.b64 _, [%0], %1;" ::"r"(bar), "r"(bytes) : "memory");
}
__device__ __forceinline__ void bulk_copy(uint32_t dst, const void* src, uint32_t bytes, uint32_t bar) {
    asm volatile("cp.async.bulk.shared::cluster.global.mbarrier::complete_tx::bytes [%0], [%1], %2, [%3];" ::"r"(dst),
                 "l"(src), "r"(bytes), "r"(bar)
                 : "memory");
}
__device__ __forceinline__ void bulk_load(uint32_t dst, const void* src, uint32_t bytes, uint32_t bar) {
    mbar_expect(bar, bytes);
    bulk_copy(dst, src, bytes, bar);
}
__device__ __forceinline__ void fence_async() { asm volatile("fence.proxy.async.shared::cta;" ::: "memory"); }
__device__ __forceinline__ bool elect_one() {
    uint32_t p;
    asm volatile("{\n.reg .pred p;\nelect.sync _|p, 0xFFFFFFFF;\nselp.u32 %0, 1, 0, p;\n}\n" : "=r"(p));
    return p != 0;
}
__device__ __forceinline__ int lane_again() {
    int t;
    asm volatile("mov.u32 %0, %%tid.x;" : "=r"(t));
    return t & 31;
}

template <int R>
__device__ __forceinline__ void load_row(uint32_t (&r)[24], uint32_t addr) {
#pragma unroll
    for (int q = 0; q < 3; q++) {
        const uint4 v = lds128(addr + q * 64);
        r[8 * q + R] = v.x; r[8 * q + 2 + R] = v.y; r[8 * q + 4 + R] = v.z; r[8 * q + 6 + R] = v.w;
    }
}
template <int R>
__device__ __forceinline__ void load_row_if(uint32_t (&r)[24], uint32_t addr, bool pred) {
#pragma unroll
    for (int q = 0; q < 3; q++)
        asm volatile("{\n.reg .pred p;\nsetp.ne.s32 p, %5, 0;\n@p ld.shared.v4.u32 {%0,%1,%2,%3}, [%4];\n}\n"
                     : "+r"(r[8 * q + R]), "+r"(r[8 * q + 2 + R]), "+r"(r[8 * q + 4 + R]), "+r"(r[8 * q + 6 + R])
                     : "r"(addr + q * 64), "r"((int)pred)
                     : "memory");
}
template <int R>
__device__ __forceinline__ void store_row_if(const uint32_t (&r)[24], uint32_t addr, bool pred) {
#pragma unroll
    for (int q = 0; q < 3; q++)
        asm volatile("{\n.reg .pred p;\nsetp.ne.s32 p, %5, 0;\n@p st.shared.v4.u32 [%0], {%1,%2,%3,%4};\n}\n" ::"r"(addr + q * 64),
                     "r"(r[8 * q + R]), "r"(r[8 * q + 2 + R]), "r"(r[8 * q + 4 + R]), "r"(r[8 * q + 6 + R]), "r"((int)pred)
                     : "memory");
}
template <int R>
__device__ __forceinline__ void output_row_if(const uint32_t (&r)[24], __nv_bfloat16* o, bool pred) {
#pragma unroll
    for (int q = 0; q < 3; q++)
        asm volatile("{\n.reg .pred p;\nsetp.ne.b32 p, %5, 0;\n@p st.global.v4.u32 [%0], {%1,%2,%3,%4};\n}\n" ::"l"(o + q * 32),
                     "r"(h2_to_bf2(r[8 * q + R])), "r"(h2_to_bf2(r[8 * q + 2 + R])), "r"(h2_to_bf2(r[8 * q + 4 + R])),
                     "r"(h2_to_bf2(r[8 * q + 6 + R])), "r"((int)pred)
                     : "memory");
}
__device__ __forceinline__ int w_src(int kg, int lane) {
    return (32 * (kg >> 2) + 8 * (lane >> 3) + 2 * (kg & 3) + ((lane >> 2) & 1)) * ROW_B + (lane & 3) * 16;
}
__device__ __forceinline__ void w_store(uint32_t dst, uint4 v) {
    sts32(dst, v.x); sts32(dst + 128, v.y); sts32(dst + 256, v.z); sts32(dst + 384, v.w);
}

__device__ __forceinline__ void gemm_bf16_issue(float (&acc)[48], uint32_t (&a)[24], uint64_t desc) {
    fence_regs(a);
    WG_FENCE();
    mma_bf16<false>(acc, &a[0], desc);
#pragma unroll
    for (int kk = 1; kk < 6; kk++) mma_bf16<true>(acc, &a[4 * kk], desc + kk * (3072 >> 4));
    WG_COMMIT();
}
template <bool EARLY>
__device__ __forceinline__ void inj_finish(float (&acc)[48], uint32_t (&inj)[24], uint32_t sbase, int lane) {
    uint32_t b[24];
    if (EARLY) load_row<0>(b, sbase + SM_BIAS + (lane & 3) * 16);
    WG_WAIT0();
    fence_regs(acc);
    if (!EARLY) load_row<0>(b, sbase + SM_BIAS + (lane & 3) * 16);
#pragma unroll
    for (int i = 0; i < 24; i++) inj[i] = add_f16x2(pack_f16(acc[2 * i], acc[2 * i + 1]), b[i & ~1]);
    const uint32_t m0 = inj[0] | inj[8] | inj[16], m1 = inj[1] | inj[9] | inj[17];
    sts8_if(sbase + SM_CNT + 12, 1, (m0 & 0x70007000u) == 0 || (m1 & 0x70007000u) == 0);
    fence_regs(inj);
}

__device__ __forceinline__ void recompute_bf16(const __nv_bfloat16* x, const __nv_bfloat16* wz, const __nv_bfloat16* bias,
                                               __nv_bfloat16* out, uint32_t sbase, int tile0, int nt, int wrp) {
    const int lane = lane_again();
    __syncthreads();
    if (wrp < 12) {
#pragma unroll
        for (int q = 0; q < 3; q++)
            w_store(sbase + SM_WZ + wrp * 1536 + q * 512 + lane * 4, __ldg((const uint4*)((const uint8_t*)wz + w_src(wrp, lane) + q * 64)));
    }
    fence_async();
    __syncthreads();
    const uint64_t dx = make_desc(sbase + SM_WX), dz = make_desc(sbase + SM_WZ);
#pragma unroll 1
    for (int j = wrp >> 2; j < nt; j += 4) {
        const size_t off = (size_t)((tile0 + j) * 64 + (wrp & 3) * 16 + (lane >> 2)) * C + (lane & 3) * 8;
        uint32_t a[24], inj[24];
        float acc[48];
#pragma unroll
        for (int i = 0; i < 6; i++) {
            const int r = i & 1, q = i >> 1;
            const uint4 v = __ldg((const uint4*)(x + off + r * 8 * C + q * 32));
            a[8 * q + r] = v.x; a[8 * q + 2 + r] = v.y; a[8 * q + 4 + r] = v.z; a[8 * q + 6 + r] = v.w;
        }
        gemm_bf16_issue(acc, a, dx);
        WG_WAIT0();
        fence_regs(acc);
#pragma unroll
        for (int i = 0; i < 24; i++) {
            const uint32_t b = __ldg((const uint32_t*)bias + 16 * (i >> 3) + 4 * (lane & 3) + ((i >> 1) & 3));
            inj[i] = add_bf16x2(pack_bf16(acc[2 * i], acc[2 * i + 1]), b);
            a[i] = inj[i];
        }
        fence_regs(inj);
#pragma unroll 1
        for (int it = 1;; it++) {
#pragma unroll
            for (int i = 0; i < 24; i++)
                a[i] = pack_bf16(tanh_f32(__uint_as_float(a[i] << 16)), tanh_f32(__uint_as_float(a[i] & 0xFFFF0000u)));
            if (it == NITER) break;
            gemm_bf16_issue(acc, a, dz);
            WG_WAIT0();
            fence_regs(acc);
#pragma unroll
            for (int i = 0; i < 24; i++) a[i] = add_bf16x2(pack_bf16(acc[2 * i], acc[2 * i + 1]), inj[i]);
            fence_regs(a);
        }
#pragma unroll
        for (int i = 0; i < 6; i++) {
            const int r = i & 1, q = i >> 1;
            *(uint4*)(out + off + r * 8 * C + q * 32) = make_uint4(a[8 * q + r], a[8 * q + 2 + r], a[8 * q + 4 + r], a[8 * q + 6 + r]);
        }
    }
}

__global__ void __launch_bounds__(NTHREADS, 1)
deq_kernel(const __nv_bfloat16* __restrict__ x, const __nv_bfloat16* __restrict__ wz, const __nv_bfloat16* __restrict__ wx,
           const __nv_bfloat16* __restrict__ bias, __nv_bfloat16* __restrict__ out, int ntiles) {
    extern __shared__ __align__(1024) uint8_t smem[];
    const int tid = threadIdx.x;
    const uint32_t sbase = (uint32_t)__cvta_generic_to_shared(smem);
    const int tile0 = blockIdx.x * 6;
    const int nt = min(6, ntiles - tile0);
    const uint32_t barX = sbase + SM_BAR;
    const uint32_t barS = barX + 40;
    const uint32_t barP = barX + 48, barC = barX + 56;
    const uint32_t barW = barX + 64, barZ = barX + 72;
    const uint32_t barRx = barX + 80, barRz = barX + 88;
    const int wrp = __reduce_max_sync(FULL, tid >> 5);

    if (wrp == 12) {
        if (elect_one()) {
            const uint8_t* x0 = (const uint8_t*)x + (size_t)tile0 * TILE_B;
            mbar_init(barRx, 1);
            asm volatile("fence.mbarrier_init.release.cluster;" ::: "memory");
            mbar_expect(barRx, W_B + ROW_B);
            bulk_copy(sbase + SM_PB, wx, W_B, barRx);
            mbar_init(barX, 1);
            mbar_init(barRz, 1);
            mbar_init(barX + 8, 1);
            mbar_init(barX + 16, 1);
            asm volatile("fence.mbarrier_init.release.cluster;" ::: "memory");
            bulk_copy(sbase + SM_BIAS, bias, ROW_B, barRx);
            mbar_expect(barX, TILE_B);
            bulk_copy(sbase + SM_PA, x0, TILE_B / 2, barX);
            bulk_load(sbase + SM_PB + W_B, wz, W_B, barRz);
            bulk_copy(sbase + SM_PA + TILE_B / 2, x0 + TILE_B / 2, TILE_B / 2, barX);
        }
        __syncwarp();
        __nanosleep(150);
        if (elect_one()) bulk_load(sbase + SM_PA + TILE_B, x + (size_t)(tile0 + min(1, nt - 1)) * (64 * C), TILE_B, barX + 8);
    }
    asm volatile("" ::: "memory");
    if (wrp == 13) {
        if (elect_one()) {
            mbar_init(barS, 1);
            mbar_init(barP, 16);
            mbar_init(barC, 12);
            mbar_init(barW, 12);
            mbar_init(barZ, 4);
            *(uint4*)(smem + SM_CNT) = make_uint4(0, 64, (0x10000u - LUT_LO) * 0x10001u, 0);
            asm volatile("fence.mbarrier_init.release.cluster;" ::: "memory");
        }
    }
    const int lane = tid & 31;
    const int wg = wrp >> 2;
    const int wrow = (wrp & 3) * 16 + (lane >> 2);

#pragma unroll 1
    for (int e = wg < 3 ? tid : tid == 448 ? LUT_N - 1 : LUT_N; e < LUT_N; e += tid == 0 ? 384 + (e >> 8) : 384) {
        float lo, hi;
        unpack_f16(LUT_LO + e * 8 + 4, lo, hi);
        const uint32_t v = pack_f16(e == LUT_N - 1 ? 1.f : tanh_f32(lo), 0.f);
#pragma unroll
        for (int j = 0; j < 8; j++) *(uint4*)(smem + SM_LUT + e * 128 + ((j ^ (lane & 7)) << 4)) = make_uint4(v, v, v, v);
    }
    __syncthreads();

    if (wg < 3) {
        mbar_wait(barRx);
        uint4 v[3];
#pragma unroll
        for (int q = 0; q < 3; q++) v[q] = lds128(sbase + SM_PB + w_src(wrp, lane) + q * 64);
        uint32_t b = 0;
        if (tid < 48) b = bf2_to_h2(lds32(sbase + SM_BIAS + tid * 4));
#pragma unroll
        for (int q = 0; q < 3; q++) w_store(sbase + SM_WX + wrp * 1536 + q * 512 + lane * 4, v[q]);
        if (tid < 48) sts32(sbase + SM_BIAS + tid * 4, b);
        sts8_if(sbase + SM_CNT + 12, 1, (b & 0x7FFFu) >= 0x7400u || (b & 0x7FFF0000u) >= 0x74000000u);
        fence_async();
        mbar_arrive_warp(barW, lane);
        if (wrp == 8) {
            if (elect_one()) bulk_load(sbase + SM_PA + 2 * TILE_B, x + (size_t)(tile0 + min(2, nt - 1)) * (64 * C), TILE_B, barX + 16);
            __syncwarp();
        }
    } else {
        mbar_wait(barRz);
        uint4 v[9];
#pragma unroll
        for (int i = 0; i < 9; i++) v[i] = lds128(sbase + SM_PB + W_B + w_src(wrp - 12, lane) + (i / 3) * 32 * ROW_B + (i % 3) * 64);
#pragma unroll
        for (int i = 0; i < 9; i++)
            w_store(sbase + SM_WZ + (wrp - 12 + (i / 3) * 4) * 1536 + (i % 3) * 512 + lane * 4,
                    make_uint4(bf2_to_h2(v[i].x), bf2_to_h2(v[i].y), bf2_to_h2(v[i].z), bf2_to_h2(v[i].w)));
        fence_async();
        mbar_arrive_warp(barZ, lane);
        mbar_wait(barZ);
        {
            uint32_t m = 0;
#pragma unroll
            for (int i = 0; i < 9; i++) {
                m = __vimax3_u16x2(m, v[i].x & 0x7FFF7FFFu, v[i].y & 0x7FFF7FFFu);
                m = __vimax3_u16x2(m, v[i].z & 0x7FFF7FFFu, v[i].w & 0x7FFF7FFFu);
            }
            sts8_if(sbase + SM_CNT + 12, 1, (m & 0xFFFFu) >= 0x3E80u || m >= 0x3E800000u);
        }
        mbar_arrive_warp(barP, lane);
        if (wrp == 12 && nt > 3) {
            mbar_wait(barW);
            mbar_wait(barX + 16);
            __nanosleep(1000);
            if (elect_one()) bulk_load(sbase + SM_PB, x + (size_t)(tile0 + 3) * (64 * C), (nt - 3) * TILE_B, barS);
        }
        __syncwarp();
    }

    Inv c;
    c.lut = __shfl_sync(FULL, sbase + SM_LUT + (lane ^ 1) * 4, lane ^ 1);
    c.neglo = lds32(sbase + SM_CNT + 8);
    c.mul = __reduce_max_sync(FULL, 0x10000010u - lane);
    c.zero = __reduce_min_sync(FULL, (uint32_t)lane);
#pragma unroll
    for (int k = 0; k < 6; k++) {
        const uint64_t d = make_desc(sbase + SM_WZ + k * 3072);
        c.dz[k] = (d & 0xFFFFFFFF00000000ull) | __reduce_max_sync(FULL, (uint32_t)d);
    }
    const uint64_t dx = make_desc(sbase + SM_WX);

    uint32_t h[24], a[24], inj[24], pn[24];
    int row0 = -1, row1 = -1;
    int cnt = 0;
    int redo = -1;
    bool work = true;
    if (wg < 3) {
        bool second = 3 + wg >= nt;
        if (second) asm volatile("bar.arrive 1, 512;" ::: "memory");
        mbar_wait(barW);
        mbar_wait(barX + wg * 8);
        work = wg < nt;
        if (!work) mbar_arrive_warp(barP, lane);
        if (work) {
            {
                const uint32_t frag = sbase + SM_PA + (wg * 64 + wrow) * ROW_B + (lane & 3) * 16;
                float acc[48];
                load_row<0>(a, frag);
                load_row<1>(a, frag + 8 * ROW_B);
                gemm_bf16_issue(acc, a, dx);
                mbar_wait(barZ);
                inj_finish<true>(acc, inj, sbase, lane);
                store_row_if<0>(inj, frag, true);
                store_row_if<1>(inj, frag + 8 * ROW_B, true);
                if (second) mbar_arrive_warp(barP, lane);
            }
            uint4 cv;
            bool fin0, fin1;
#pragma unroll 1
            while (true) {
                uint32_t p[24];
                step<P_INJ>(Seq<SEQ0>(), h, a, p, inj, c);
#pragma unroll 1
                for (int it = 2; it < KCHK; it++) step<P_SUM>(Seq<SEQ1>(), h, a, p, inj, c);
                mbar_wait(second ? barP : barS);
                step<P_SUM>(Seq<SEQK>(), h, a, p, inj, c);
                cv = lds128(sbase + SM_CNT);
                const int lane = lane_again();
                uint32_t d0 = 0, d1 = 0;
#pragma unroll
                for (int i = 0; i < 24; i++) {
                    pn[i] = add_f16x2(h[i], inj[i]);
                    if (i & 1) d1 |= pn[i] ^ p[i]; else d0 |= pn[i] ^ p[i];
                }
                fin0 = ((__ballot_sync(FULL, d0 != 0) >> (lane & ~3)) & 0xF) == 0;
                fin1 = ((__ballot_sync(FULL, d1 != 0) >> (lane & ~3)) & 0xF) == 0;
                if (second) break;
                const int wrow = (wrp & 3) * 16 + (lane >> 2);
                const uint32_t below = (1u << (lane & ~3)) - 1;
                const uint32_t frag = sbase + SM_PB + (wg * 64 + wrow) * ROW_B + (lane & 3) * 16;
                const uint32_t m0 = __ballot_sync(FULL, !fin0 && (lane & 3) == 0);
                const uint32_t m1 = __ballot_sync(FULL, !fin1 && (lane & 3) == 0);
                int base = atoms_add_lane0(sbase + SM_CNT, __popc(m0) + __popc(m1), lane);
                int rank = (lane & 1) ? __popc(m0) + __popc(m1 & below) : __popc(m0 & below);
                if ((lane & 2) || ((lane & 1) ? fin1 : fin0)) rank = -1;
                asm volatile("" : "+r"(rank));
                uint32_t xf[24];
                float acc[48];
                load_row<0>(xf, frag);
                load_row<1>(xf, frag + 8 * ROW_B);
                store_row_if<0>(pn, frag, !fin0);
                store_row_if<1>(pn, frag + 8 * ROW_B, !fin1);
#pragma unroll
                for (int i = 0; i < 24; i++)
                    if (!((LUTMASK >> i) & 1)) a[i] ^= c.zero;
                __nv_bfloat16* o = out + (size_t)((tile0 + wg) * 64 + wrow) * C + (lane & 3) * 8;
                output_row_if<0>(a, o, fin0);
                output_row_if<1>(a, o + 8 * C, fin1);
                gemm_bf16_issue(acc, xf, dx);
                base = __shfl_sync(FULL, base, 0);
                sts8_if(sbase + SM_LIST + base + rank, wg * 64 + wrow + (lane & 1) * 8, rank >= 0);
                asm volatile("bar.arrive 1, 512;" ::: "memory");
                inj_finish<false>(acc, inj, sbase, lane);
                mbar_arrive_warp(barP, lane);
                second = true;
            }
            const int lane = lane_again(), wrow = (wrp & 3) * 16 + (lane >> 2);
            row0 = (tile0 + wg + (3 + wg < nt ? 3 : 0)) * 64 + wrow;
            row1 = row0 + 8;
            redo = __reduce_max_sync(FULL, (int)cv.w);
            const int cnt = cv.x;
            if (__reduce_max_sync(FULL, (int)cv.y) < cnt) {
                const uint32_t m0 = __ballot_sync(FULL, fin0 && (lane & 3) == 0);
                const uint32_t m1 = __ballot_sync(FULL, fin1 && (lane & 3) == 0);
                const int base = __reduce_max_sync(FULL, atoms_add_lane0(sbase + SM_CNT + 4, __popc(m0) + __popc(m1), lane));
                if (base < cnt && (m0 | m1) != 0) {
                    const uint32_t below = (1u << (lane & ~3)) - 1;
                    const uint32_t pool = sbase + SM_PA + (lane & 3) * 16;
                    const int i0 = base + __popc(m0 & below), i1 = base + __popc(m0) + __popc(m1 & below);
                    const bool t0 = fin0 && i0 < cnt, t1 = fin1 && i1 < cnt;
                    const int s0 = lds8(sbase + SM_LIST + (t0 ? i0 : 0)), s1 = lds8(sbase + SM_LIST + (t1 ? i1 : 0));
#pragma unroll
                    for (int i = 0; i < 24; i++)
                        if (!((LUTMASK >> i) & 1)) a[i] ^= c.zero;
                    output_row_if<0>(a, out + (size_t)row0 * C + (lane & 3) * 8, t0);
                    load_row_if<0>(pn, pool + s0 * ROW_B + 3 * TILE_B, t0);
                    load_row_if<1>(pn, pool + s1 * ROW_B + 3 * TILE_B, t1);
                    load_row_if<0>(inj, pool + s0 * ROW_B, t0);
                    load_row_if<1>(inj, pool + s1 * ROW_B, t1);
                    output_row_if<1>(a, out + (size_t)row1 * C + (lane & 3) * 8, t1);
                    if (t0) row0 = tile0 * 64 + s0;
                    if (t1) row1 = tile0 * 64 + s1;
                }
            }
        }
        mbar_arrive_warp(barC, lane_again());
    } else {
        asm volatile("bar.sync 1, 512;" ::: "memory");
        cnt = lds32(sbase + SM_CNT);
    }
    cnt = __reduce_max_sync(FULL, cnt);
    if (wg == 3) work = cnt > 0;

    int next = 0;
#pragma unroll 1
    while (work) {
        if (wg == 3) {
            const int lane = lane_again(), wrow = (wrp & 3) * 16 + (lane >> 2);
            const uint32_t pool = sbase + SM_PA + (lane & 3) * 16;
            const bool t0 = next + wrow < cnt, t1 = next + wrow + 8 < cnt;
            const int s0 = lds8(sbase + SM_LIST + next + (t0 ? wrow : 0)), s1 = lds8(sbase + SM_LIST + next + (t1 ? wrow + 8 : 0));
            load_row<0>(inj, pool + s0 * ROW_B);
            load_row<1>(inj, pool + s1 * ROW_B);
            load_row<0>(pn, pool + s0 * ROW_B + 3 * TILE_B);
            load_row<1>(pn, pool + s1 * ROW_B + 3 * TILE_B);
            row0 = t0 ? tile0 * 64 + s0 : -1;
            row1 = t1 ? tile0 * 64 + s1 : -1;
        }
        fence_regs(pn);
        fence_regs(inj);
        step<P_GIVEN>(Seq<SEQG>(), h, a, pn, inj, c);
#pragma unroll 1
        for (int it = KCHK + 2; it < NITER; it++) {
            uint32_t p[24];
            step<P_SUM>(Seq<SEQ2>(), h, a, p, inj, c);
        }
        step<P_LAST>(Seq<SEQL>(), h, a, pn, inj, c);
        const int col = (lane_again() & 3) * 8;
        output_row_if<0>(a, out + (size_t)row0 * C + col, row0 >= 0);
        output_row_if<1>(a, out + (size_t)row1 * C + col, row1 >= 0);
        if (wg < 3) break;
        mbar_wait(barC);
        const int claimed = __reduce_max_sync(FULL, lds32(sbase + SM_CNT + 4));
        next = next == 0 ? claimed : next + 64;
        work = next < cnt;
    }

    if (redo < 0) {
        mbar_wait(barP);
        redo = __reduce_max_sync(FULL, lds32(sbase + SM_CNT + 12));
    }
    if (redo != 0) recompute_bf16(x, wz, bias, out, sbase, tile0, nt, wrp);
}

}

extern "C" void kernel_launch(void* const* d_in, const int* in_sizes, int n_in, void* d_out, int out_size) {
    const __nv_bfloat16* x = (const __nv_bfloat16*)d_in[0];
    const __nv_bfloat16* wz = (const __nv_bfloat16*)d_in[1];
    const __nv_bfloat16* wx = (const __nv_bfloat16*)d_in[2];
    const __nv_bfloat16* b = (const __nv_bfloat16*)d_in[3];
    __nv_bfloat16* out = (__nv_bfloat16*)d_out;
    static bool init = false;
    if (!init) {
        init = true;
        cudaFuncSetAttribute(deq_kernel, cudaFuncAttributeMaxDynamicSharedMemorySize, SM_TOTAL);
    }
    const int ntiles = in_sizes[0] / (64 * C);
    deq_kernel<<<(ntiles + 5) / 6, NTHREADS, SM_TOTAL>>>(x, wz, wx, b, out, ntiles);
}
```
